```python
import torch

def _softmax(x, axis=-1):
    return torch.softmax(x, dim=axis)
def _gelu(x):
    return torch.nn.functional.gelu(x, approximate="tanh")
def _silu(x):
    return torch.nn.functional.silu(x)
def _sigmoid(x):
    return torch.sigmoid(x)
def _layernorm(x, axis=-1, eps=1e-5):
    m = x.mean(dim=axis, keepdim=True)
    v = x.var(dim=axis, keepdim=True, unbiased=False)
    return (x - m) / torch.sqrt(v + eps)
def _scatter_add(tgt, idx, src, axis=0):
    return tgt.clone().index_add_(axis, idx, src)
def _segment_sum(src, seg, n):
    out = torch.zeros((n,) + src.shape[1:], dtype=src.dtype)
    return out.index_add_(0, seg, src)
def _pad(x, pw):
    flat = tuple(v for pair in reversed(pw) for v in pair)
    return torch.nn.functional.pad(x, flat)

kernel_name = 'parallel_sum__ssm_conv_h3__glu_gated_reglu__prompt'

def setup_inputs():

    _w = (lambda a: (lambda t: t.to(torch.bfloat16) if t.is_floating_point() else t)(torch.as_tensor(a)))
    def _A_setup():
        B, S, D = 1, 2048, 576
        ks = 4
        return {
            "q": _w((lambda *s: torch.randn(*s, dtype=torch.bfloat16) * 0.05)(B, S, D)),
            "k": _w((lambda *s: torch.randn(*s, dtype=torch.bfloat16) * 0.2)(B, S, D)),
            "v": _w((lambda *s: torch.randn(*s, dtype=torch.bfloat16) * 0.2)(B, S, D)),
            "shift_k": _w((lambda *s: torch.randn(*s, dtype=torch.bfloat16) * 0.2)(D, ks) * 0.5),
            "ssm_k": _w((lambda *s: torch.randn(*s, dtype=torch.bfloat16) * 0.4)(D, S) * (1.0 / S ** 0.5)),
            "ssm_D": _w((lambda *s: torch.randn(*s, dtype=torch.bfloat16) * 0.2)(D)),
        }
    _A_in = _A_setup()

    def _B_setup():
        B, S, D, F = 1, 2048, 576, 4608
        return {
            "x": _w((lambda *s: torch.randn(*s, dtype=torch.bfloat16) * 0.05)(B, S, D)),
            "W_gate": _w((lambda *s: torch.randn(*s, dtype=torch.bfloat16) * 0.2)(D, F) * (2.0 / D) ** 0.5),
            "W_up": _w((lambda *s: torch.randn(*s, dtype=torch.bfloat16) * 0.2)(D, F) * (2.0 / D) ** 0.5),
            "W_down": _w((lambda *s: torch.randn(*s, dtype=torch.bfloat16) * 0.2)(F, D) * (1.0 / F) ** 0.5),
        }
    _B_in = _B_setup()

    return {
        "A_q": _A_in["q"],
        "A_k": _A_in["k"],
        "A_v": _A_in["v"],
        "A_shift_k": _A_in["shift_k"],
        "A_ssm_k": _A_in["ssm_k"],
        "A_ssm_D": _A_in["ssm_D"],
        "B_x": _B_in["x"],
        "B_W_gate": _B_in["W_gate"],
        "B_W_up": _B_in["W_up"],
        "B_W_down": _B_in["W_down"],
    }

def reference(A_q, A_k, A_v, A_shift_k, A_ssm_k, A_ssm_D, B_x, B_W_gate, B_W_up, B_W_down):
    def _A_ref(q, k, v, shift_k, ssm_k, ssm_D):
        B, S, D = q.shape
        ks = shift_k.shape[-1]
        k_pad = _pad(k, ((0, 0), (ks - 1, 0), (0, 0)))
        k_shift = torch.zeros_like(k)
        for t in range(ks):
            k_shift = k_shift + k_pad[:, t:t + S, :] * shift_k[:, ks - 1 - t][None, None, :]
        kv = k_shift * v
        L = 2 * S
        kv_pad = _pad(kv, ((0, 0), (0, S), (0, 0)))
        kf_pad = _pad(ssm_k, ((0, 0), (0, S)))
        kv_f = (lambda x, axes=(-2,-1): torch.fft.rfft2(x.float(), dim=axes))(kv_pad[:, None, :, :], axes=(1, 2))
        kf_f = (lambda x, axes=(-2,-1): torch.fft.rfft2(x.float(), dim=axes))(kf_pad[:, None, :], axes=(1, 2))
        kf_f = (lambda x, *d: x.permute(*d))(kf_f, 1, 2, 0)
        y_f = kv_f * kf_f[None, :, :, :]
        y = (lambda x, s, axes=(-2,-1): torch.fft.irfft2(x, s=s, dim=axes).to(torch.bfloat16))(y_f, (1, L), axes=(1, 2))[:, 0, :S, :]
        y = y + kv * ssm_D[None, None, :]
        return q * y

    def _B_ref(x, W_gate, W_up, W_down):
        gate = torch.einsum("bsd,df->bsf", x, W_gate)
        up = torch.einsum("bsd,df->bsf", x, W_up)
        gate = gate * (lambda x, dt: x.to(dt))(gate > 0, gate.dtype)
        h = gate * up
        return torch.einsum("bsf,fd->bsd", h, W_down)

    x = A_q
    xn = _layernorm(x, axis=-1)
    return x + _A_ref(xn, A_k, A_v, A_shift_k, A_ssm_k, A_ssm_D) + _B_ref(xn, B_W_gate, B_W_up, B_W_down)
```

```cpp
#include <cuda_runtime.h>
#include <cuda_bf16.h>
#include <cuda.h>
#include <stdint.h>

namespace ffn {

constexpr int S_ = 2048, D_ = 576, F_ = 4608;
constexpr int NCTA = 132;
constexpr int NTHREADS = 384;
constexpr int G1_CLUSTERS = 40;
constexpr int G2_CLUSTERS = 24;
constexpr int G1_FSPAN = 928;

constexpr int G1_STAGES = 8;
constexpr int G1_STAGE_BYTES = 24576;
constexpr int G1_X_OFF = 2 * G1_STAGE_BYTES;
constexpr int G1_HST_OFF = G1_STAGES * G1_STAGE_BYTES;
constexpr int G2_STAGES = 10;
constexpr int G2_STAGE_BYTES = 20480;
constexpr int G2_Y_OFF = 4 * G2_STAGE_BYTES;
constexpr int G2_O_OFF = G2_Y_OFF + 49152;
constexpr int PA_U_OFF = 0;
constexpr int PA_K_OFF = 49152;
constexpr int PA_K_BOX = 17408;
constexpr int PA_V_OFF = PA_K_OFF + 3 * PA_K_BOX;
constexpr int CV_P_OFF = 4 * G2_STAGE_BYTES;
constexpr int CV_P_BYTES = 32768 + 4096;
constexpr int CV_U_OFF = CV_P_OFF + 2 * CV_P_BYTES;
constexpr int CV_U_BYTES = 4352;
constexpr int CV_K_OFF = CV_U_OFF + 4 * CV_U_BYTES;
constexpr int CV_K_BYTES = 8448;
constexpr int G1_CU_OFF = G1_HST_OFF + 16384;
constexpr int BAR_OFF = G1_CU_OFF + 2 * CV_U_BYTES;
constexpr int SMEM_BYTES = BAR_OFF + 1024 + 1024;

constexpr int B_FULL = 0;
constexpr int B_EMPTY = 10;
constexpr int B_XFULL = 20;
constexpr int B_XFREE = 29;
constexpr int B_HFULL = 30;
constexpr int B_HEMPTY = 32;
constexpr int B_KVFULL = 34;
constexpr int B_UFULL = 37;
constexpr int B_KRAW = 41;
constexpr int B_YFULL = 43;
constexpr int B_PFREE = 45;
constexpr int B_PADONE = 46;
constexpr int B_KFULL = 47;
constexpr int B_CEMPTY = 51;

struct Params {
  CUtensorMap m_x, m_wg, m_wu, m_wd, m_h, m_k, m_v, m_u, m_us, m_y;
  const __nv_bfloat16* x;
  __nv_bfloat16* out;
  const __nv_bfloat16* shift_k;
  const __nv_bfloat16* ssm_k;
  const __nv_bfloat16* ssm_D;
  uint32_t zero;
};

__device__ __nv_bfloat16 g_h[(size_t)S_ * F_];
__device__ __nv_bfloat16 g_uT[(size_t)D_ * S_];
__device__ __nv_bfloat16 g_yT[(size_t)D_ * S_];
__device__ float2 g_stats[S_];
__device__ uint32_t g_hprog[16 * 16];
__device__ uint32_t g_ucnt[4 * 8];
__device__ uint32_t g_ycnt[4 * 8];
__device__ uint32_t g_epoch;
__device__ uint32_t g_done;
#define PROF(i) do {} while (0)
#define PROF_G(i) do {} while (0)
#define PROF_VAL(i, v) do {} while (0)
#define CLK_BEGIN(v) do {} while (0)
#define CLK_END(v) do {} while (0)

constexpr uint32_t SPIN_LIMIT = 1u << 24;

__device__ __forceinline__ void mbar_init(uint32_t bar, uint32_t cnt) {
  asm volatile("mbarrier.init.shared::cta.b64 [%0], %1;" ::"r"(bar), "r"(cnt) : "memory");
}
__device__ __forceinline__ void mbar_expect_tx(uint32_t bar, uint32_t bytes) {
  asm volatile("mbarrier.arrive.expect_tx.shared::cta.b64 _, [%0], %1;" ::"r"(bar), "r"(bytes) : "memory");
}
__device__ __forceinline__ void mbar_arrive(uint32_t bar) {
  asm volatile("mbarrier.arrive.shared::cta.b64 _, [%0];" ::"r"(bar) : "memory");
}
__device__ __forceinline__ void mbar_arrive_cta(uint32_t bar, uint32_t cta) {
  asm volatile("{\n.reg .b32 ra;\nmapa.shared::cluster.u32 ra, %0, %1;\nmbarrier.arrive.shared::cluster.b64 _, [ra];\n}"
               ::"r"(bar), "r"(cta) : "memory");
}
__device__ __forceinline__ bool mbar_try(uint32_t bar, uint32_t parity) {
  uint32_t ok;
  asm volatile("{\n.reg .pred p;\nmbarrier.try_wait.parity.shared::cta.b64 p, [%1], %2;\nselp.u32 %0, 1, 0, p;\n}"
               : "=r"(ok) : "r"(bar), "r"(parity) : "memory");
  return ok != 0;
}
__device__ __forceinline__ void mbar_wait(uint32_t bar, uint32_t parity) {
  asm volatile("{\n.reg .pred p;\n.reg .u32 n;\nmov.u32 n, 0;\n"
               "WAIT_LOOP:\n"
               "mbarrier.try_wait.parity.shared::cta.b64 p, [%0], %1;\n"
               "@p bra WAIT_DONE;\n"
               "add.u32 n, n, 1;\nsetp.lt.u32 p, n, 0x1000000;\n@p bra WAIT_LOOP;\n"
               "trap;\n"
               "WAIT_DONE:\n}" ::"r"(bar), "r"(parity) : "memory");
}
__device__ __forceinline__ uint32_t spin_ge(const uint32_t* p, uint32_t target) {
  uint32_t v;
  asm volatile("{\n.reg .pred p;\n.reg .u32 n;\nmov.u32 n, 0;\n"
               "SPIN_LOOP:\n"
               "ld.relaxed.gpu.global.u32 %0, [%1];\n"
               "setp.ge.u32 p, %0, %2;\n"
               "@p bra SPIN_DONE;\n"
               "add.u32 n, n, 1;\nsetp.lt.u32 p, n, 0x1000000;\n@p bra SPIN_LOOP;\n"
               "trap;\n"
               "SPIN_DONE:\n}" : "=&r"(v) : "l"(p), "r"(target) : "memory");
  return v;
}
__device__ __forceinline__ void trap_if(bool c) {
  asm volatile("{\n.reg .pred p;\nsetp.ne.u32 p, %0, 0;\n@p trap;\n}" ::"r"((uint32_t)c));
}
__device__ __forceinline__ void tma_load_2d(uint32_t dst, const CUtensorMap* m, int c0, int c1, uint32_t bar) {
  asm volatile("cp.async.bulk.tensor.2d.shared::cluster.global.mbarrier::complete_tx::bytes [%0], [%1, {%3, %4}], [%2];"
               ::"r"(dst), "l"(m), "r"(bar), "r"(c0), "r"(c1) : "memory");
}
__device__ __forceinline__ void tma_load_2d_mc(uint32_t dst, const CUtensorMap* m, int c0, int c1, uint32_t bar) {
  asm volatile("cp.async.bulk.tensor.2d.shared::cluster.global.mbarrier::complete_tx::bytes.multicast::cluster [%0], [%1, {%3, %4}], [%2], %5;"
               ::"r"(dst), "l"(m), "r"(bar), "r"(c0), "r"(c1), "h"((uint16_t)3) : "memory");
}
__device__ __forceinline__ void tma_load_3d_mc(uint32_t dst, const CUtensorMap* m, int c0, int c1, int c2, uint32_t bar) {
  asm volatile("cp.async.bulk.tensor.3d.shared::cluster.global.mbarrier::complete_tx::bytes.multicast::cluster [%0], [%1, {%3, %4, %5}], [%2], %6;"
               ::"r"(dst), "l"(m), "r"(bar), "r"(c0), "r"(c1), "r"(c2), "h"((uint16_t)3) : "memory");
}
__device__ __forceinline__ void tma_load_4d(uint32_t dst, const CUtensorMap* m, int c0, int c1, int c2, int c3, uint32_t bar) {
  asm volatile("cp.async.bulk.tensor.4d.shared::cluster.global.mbarrier::complete_tx::bytes [%0], [%1, {%3, %4, %5, %6}], [%2];"
               ::"r"(dst), "l"(m), "r"(bar), "r"(c0), "r"(c1), "r"(c2), "r"(c3) : "memory");
}
__device__ __forceinline__ void tma_store_2d(const CUtensorMap* m, uint32_t src, int c0, int c1) {
  asm volatile("cp.async.bulk.tensor.2d.global.shared::cta.bulk_group [%0, {%2, %3}], [%1];"
               ::"l"(m), "r"(src), "r"(c0), "r"(c1) : "memory");
}
__device__ __forceinline__ void bulk_commit() { asm volatile("cp.async.bulk.commit_group;" ::: "memory"); }
__device__ __forceinline__ void bulk_wait_read0() { asm volatile("cp.async.bulk.wait_group.read 0;" ::: "memory"); }
__device__ __forceinline__ void bulk_wait0() { asm volatile("cp.async.bulk.wait_group 0;" ::: "memory"); }
__device__ __forceinline__ void fence_async_smem() { asm volatile("fence.proxy.async.shared::cta;" ::: "memory"); }
__device__ __forceinline__ void fence_async_global() { asm volatile("fence.proxy.async.global;" ::: "memory"); }
__device__ __forceinline__ void prefetch_map(const CUtensorMap* m) {
  asm volatile("prefetch.tensormap [%0];" ::"l"(m) : "memory");
}
__device__ __forceinline__ void cluster_arrive() { asm volatile("barrier.cluster.arrive.relaxed.aligned;" ::: "memory"); }
__device__ __forceinline__ void cluster_wait() { asm volatile("barrier.cluster.wait.acquire.aligned;" ::: "memory"); }
__device__ __forceinline__ void named_sync(int id, int n) { asm volatile("bar.sync %0, %1;" ::"r"(id), "r"(n) : "memory"); }
__device__ __forceinline__ void wg_fence() { asm volatile("wgmma.fence.sync.aligned;" ::: "memory"); }
__device__ __forceinline__ void wg_commit() { asm volatile("wgmma.commit_group.sync.aligned;" ::: "memory"); }
template <int N> __device__ __forceinline__ void wg_wait() {
  asm volatile("wgmma.wait_group.sync.aligned %0;" ::"n"(N) : "memory");
}
__device__ __forceinline__ uint32_t ld_acquire(const uint32_t* p) {
  uint32_t v;
  asm volatile("ld.acquire.gpu.global.u32 %0, [%1];" : "=r"(v) : "l"(p) : "memory");
  return v;
}
__device__ __forceinline__ uint32_t ld_relaxed(const uint32_t* p) {
  uint32_t v;
  asm volatile("ld.relaxed.gpu.global.u32 %0, [%1];" : "=r"(v) : "l"(p) : "memory");
  return v;
}
__device__ __forceinline__ void st_release(uint32_t* p, uint32_t v) {
  asm volatile("st.release.gpu.global.u32 [%0], %1;" ::"l"(p), "r"(v) : "memory");
}
__device__ __forceinline__ void st_relaxed(uint32_t* p, uint32_t v) {
  asm volatile("st.relaxed.gpu.global.u32 [%0], %1;" ::"l"(p), "r"(v) : "memory");
}
__device__ __forceinline__ void red_relaxed_add(uint32_t* p, uint32_t v) {
  asm volatile("red.relaxed.gpu.global.add.u32 [%0], %1;" ::"l"(p), "r"(v) : "memory");
}
__device__ __forceinline__ void red_release_add(uint32_t* p, uint32_t v) {
  asm volatile("red.release.gpu.global.add.u32 [%0], %1;" ::"l"(p), "r"(v) : "memory");
}
__device__ __forceinline__ void ldsm_x4(uint32_t (&r)[4], uint32_t addr) {
  asm volatile("ldmatrix.sync.aligned.m8n8.x4.shared.b16 {%0, %1, %2, %3}, [%4];"
               : "=r"(r[0]), "=r"(r[1]), "=r"(r[2]), "=r"(r[3]) : "r"(addr) : "memory");
}
__device__ __forceinline__ void ldsm_x4_t(uint32_t (&r)[4], uint32_t addr) {
  asm volatile("ldmatrix.sync.aligned.m8n8.x4.trans.shared.b16 {%0, %1, %2, %3}, [%4];"
               : "=r"(r[0]), "=r"(r[1]), "=r"(r[2]), "=r"(r[3]) : "r"(addr) : "memory");
}
__device__ __forceinline__ void stsm_x4(uint32_t addr, uint32_t r0, uint32_t r1, uint32_t r2, uint32_t r3) {
  asm volatile("stmatrix.sync.aligned.m8n8.x4.shared.b16 [%0], {%1, %2, %3, %4};"
               ::"r"(addr), "r"(r0), "r"(r1), "r"(r2), "r"(r3) : "memory");
}
__device__ __forceinline__ void mma_ones(float (&c)[4], const uint32_t (&a)[4]) {
  asm volatile("mma.sync.aligned.m16n8k16.row.col.f32.bf16.bf16.f32 {%0, %1, %2, %3}, {%4, %5, %6, %7}, {%8, %8}, {%0, %1, %2, %3};"
               : "+f"(c[0]), "+f"(c[1]), "+f"(c[2]), "+f"(c[3])
               : "r"(a[0]), "r"(a[1]), "r"(a[2]), "r"(a[3]), "r"(0x3F803F80u));
}
__device__ __forceinline__ uint32_t bf2_sub(uint32_t a, uint32_t b) {
  uint32_t d;
  asm("sub.rn.bf16x2 %0, %1, %2;" : "=r"(d) : "r"(a), "r"(b));
  return d;
}
__device__ __forceinline__ uint32_t bf2_add(uint32_t a, uint32_t b) {
  uint32_t d;
  asm("add.rn.bf16x2 %0, %1, %2;" : "=r"(d) : "r"(a), "r"(b));
  return d;
}
__device__ __forceinline__ uint32_t bf2_mul(uint32_t a, uint32_t b) {
  uint32_t d;
  asm("mul.rn.bf16x2 %0, %1, %2;" : "=r"(d) : "r"(a), "r"(b));
  return d;
}
__device__ __forceinline__ uint32_t pack_bf2(float lo, float hi) {
  uint32_t d;
  asm("cvt.rn.bf16x2.f32 %0, %1, %2;" : "=r"(d) : "f"(hi), "f"(lo));
  return d;
}
__device__ __forceinline__ uint32_t pack_bf2_relu(float lo, float hi) {
  uint32_t d;
  asm("cvt.rn.relu.bf16x2.f32 %0, %1, %2;" : "=r"(d) : "f"(hi), "f"(lo));
  return d;
}
__device__ __forceinline__ float bf_lo(uint32_t v) { return __uint_as_float(v << 16); }
__device__ __forceinline__ float bf_hi(uint32_t v) { return __uint_as_float(v & 0xffff0000u); }
__device__ __forceinline__ float bf_round(float v) { return __bfloat162float(__float2bfloat16_rn(v)); }
__device__ __forceinline__ uint32_t desc_lo(uint32_t addr, uint32_t lbo) { return ((addr & 0x3FFFFu) >> 4) | ((lbo >> 4) << 16); }

__device__ __forceinline__ void wgmma_rs_n64_tb(float (&d)[32], uint32_t a0, uint32_t a1, uint32_t a2, uint32_t a3, uint32_t descB, int scaleD) {
  asm volatile("{\n.reg .pred p;\n.reg .b64 db;\nmov.b64 db, {%36, 0x80000020};\nsetp.ne.b32 p, %37, 0;\n"
    "wgmma.mma_async.sync.aligned.m64n64k16.f32.bf16.bf16 "
    "{%0, %1, %2, %3, %4, %5, %6, %7, %8, %9, %10, %11, %12, %13, %14, %15, %16, %17, %18, %19, %20, %21, %22, %23, %24, %25, %26, %27, %28, %29, %30, %31}, "
    "{%32, %33, %34, %35}, db, p, 1, 1, 1;\n}\n"
    : "+f"(d[0]), "+f"(d[1]), "+f"(d[2]), "+f"(d[3]), "+f"(d[4]), "+f"(d[5]), "+f"(d[6]), "+f"(d[7]), "+f"(d[8]), "+f"(d[9]), "+f"(d[10]), "+f"(d[11]), "+f"(d[12]), "+f"(d[13]), "+f"(d[14]), "+f"(d[15]), "+f"(d[16]), "+f"(d[17]), "+f"(d[18]), "+f"(d[19]), "+f"(d[20]), "+f"(d[21]), "+f"(d[22]), "+f"(d[23]), "+f"(d[24]), "+f"(d[25]), "+f"(d[26]), "+f"(d[27]), "+f"(d[28]), "+f"(d[29]), "+f"(d[30]), "+f"(d[31])
    : "r"(a0), "r"(a1), "r"(a2), "r"(a3), "r"(descB), "r"(scaleD));
}
__device__ __forceinline__ void wgmma_rs_n64_tb64(float (&d)[32], uint32_t a0, uint32_t a1, uint32_t a2, uint32_t a3, uint64_t descB, int scaleD) {
  asm volatile("{\n.reg .pred p;\nsetp.ne.b32 p, %37, 0;\n"
    "wgmma.mma_async.sync.aligned.m64n64k16.f32.bf16.bf16 "
    "{%0, %1, %2, %3, %4, %5, %6, %7, %8, %9, %10, %11, %12, %13, %14, %15, %16, %17, %18, %19, %20, %21, %22, %23, %24, %25, %26, %27, %28, %29, %30, %31}, "
    "{%32, %33, %34, %35}, %36, p, 1, 1, 1;\n}\n"
    : "+f"(d[0]), "+f"(d[1]), "+f"(d[2]), "+f"(d[3]), "+f"(d[4]), "+f"(d[5]), "+f"(d[6]), "+f"(d[7]), "+f"(d[8]), "+f"(d[9]), "+f"(d[10]), "+f"(d[11]), "+f"(d[12]), "+f"(d[13]), "+f"(d[14]), "+f"(d[15]), "+f"(d[16]), "+f"(d[17]), "+f"(d[18]), "+f"(d[19]), "+f"(d[20]), "+f"(d[21]), "+f"(d[22]), "+f"(d[23]), "+f"(d[24]), "+f"(d[25]), "+f"(d[26]), "+f"(d[27]), "+f"(d[28]), "+f"(d[29]), "+f"(d[30]), "+f"(d[31])
    : "r"(a0), "r"(a1), "r"(a2), "r"(a3), "l"(descB), "r"(scaleD));
}
__device__ __forceinline__ void wgmma_ss_n192_tb(float (&d)[96], uint32_t descA, uint32_t descB, int scaleD) {
  asm volatile("{\n.reg .pred p;\n.reg .b64 da, db;\nmov.b64 da, {%96, 0x80000020};\nmov.b64 db, {%97, 0x40000040};\nsetp.ne.b32 p, %98, 0;\n"
    "wgmma.mma_async.sync.aligned.m64n192k16.f32.bf16.bf16 "
    "{%0, %1, %2, %3, %4, %5, %6, %7, %8, %9, %10, %11, %12, %13, %14, %15, %16, %17, %18, %19, %20, %21, %22, %23, %24, %25, %26, %27, %28, %29, %30, %31, %32, %33, %34, %35, %36, %37, %38, %39, %40, %41, %42, %43, %44, %45, %46, %47, %48, %49, %50, %51, %52, %53, %54, %55, %56, %57, %58, %59, %60, %61, %62, %63, %64, %65, %66, %67, %68, %69, %70, %71, %72, %73, %74, %75, %76, %77, %78, %79, %80, %81, %82, %83, %84, %85, %86, %87, %88, %89, %90, %91, %92, %93, %94, %95}, "
    "da, db, p, 1, 1, 0, 1;\n}\n"
    : "+f"(d[0]), "+f"(d[1]), "+f"(d[2]), "+f"(d[3]), "+f"(d[4]), "+f"(d[5]), "+f"(d[6]), "+f"(d[7]), "+f"(d[8]), "+f"(d[9]), "+f"(d[10]), "+f"(d[11]), "+f"(d[12]), "+f"(d[13]), "+f"(d[14]), "+f"(d[15]), "+f"(d[16]), "+f"(d[17]), "+f"(d[18]), "+f"(d[19]), "+f"(d[20]), "+f"(d[21]), "+f"(d[22]), "+f"(d[23]), "+f"(d[24]), "+f"(d[25]), "+f"(d[26]), "+f"(d[27]), "+f"(d[28]), "+f"(d[29]), "+f"(d[30]), "+f"(d[31]), "+f"(d[32]), "+f"(d[33]), "+f"(d[34]), "+f"(d[35]), "+f"(d[36]), "+f"(d[37]), "+f"(d[38]), "+f"(d[39]), "+f"(d[40]), "+f"(d[41]), "+f"(d[42]), "+f"(d[43]), "+f"(d[44]), "+f"(d[45]), "+f"(d[46]), "+f"(d[47]), "+f"(d[48]), "+f"(d[49]), "+f"(d[50]), "+f"(d[51]), "+f"(d[52]), "+f"(d[53]), "+f"(d[54]), "+f"(d[55]), "+f"(d[56]), "+f"(d[57]), "+f"(d[58]), "+f"(d[59]), "+f"(d[60]), "+f"(d[61]), "+f"(d[62]), "+f"(d[63]), "+f"(d[64]), "+f"(d[65]), "+f"(d[66]), "+f"(d[67]), "+f"(d[68]), "+f"(d[69]), "+f"(d[70]), "+f"(d[71]), "+f"(d[72]), "+f"(d[73]), "+f"(d[74]), "+f"(d[75]), "+f"(d[76]), "+f"(d[77]), "+f"(d[78]), "+f"(d[79]), "+f"(d[80]), "+f"(d[81]), "+f"(d[82]), "+f"(d[83]), "+f"(d[84]), "+f"(d[85]), "+f"(d[86]), "+f"(d[87]), "+f"(d[88]), "+f"(d[89]), "+f"(d[90]), "+f"(d[91]), "+f"(d[92]), "+f"(d[93]), "+f"(d[94]), "+f"(d[95])
    : "r"(descA), "r"(descB), "r"(scaleD));
}
__device__ __forceinline__ void wgmma_conv_n128(float (&d)[64], uint32_t a0, uint32_t a1, uint32_t a2, uint32_t a3, uint32_t descB, int scaleD) {
  asm volatile("{\n.reg .pred p;\n.reg .b64 db;\nmov.b64 db, {%68, 0x00000008};\nsetp.ne.b32 p, %69, 0;\n"
    "wgmma.mma_async.sync.aligned.m64n128k16.f32.bf16.bf16 "
    "{%0, %1, %2, %3, %4, %5, %6, %7, %8, %9, %10, %11, %12, %13, %14, %15, %16, %17, %18, %19, %20, %21, %22, %23, %24, %25, %26, %27, %28, %29, %30, %31, %32, %33, %34, %35, %36, %37, %38, %39, %40, %41, %42, %43, %44, %45, %46, %47, %48, %49, %50, %51, %52, %53, %54, %55, %56, %57, %58, %59, %60, %61, %62, %63}, "
    "{%64, %65, %66, %67}, db, p, 1, 1, 0;\n}\n"
    : "+f"(d[0]), "+f"(d[1]), "+f"(d[2]), "+f"(d[3]), "+f"(d[4]), "+f"(d[5]), "+f"(d[6]), "+f"(d[7]), "+f"(d[8]), "+f"(d[9]), "+f"(d[10]), "+f"(d[11]), "+f"(d[12]), "+f"(d[13]), "+f"(d[14]), "+f"(d[15]), "+f"(d[16]), "+f"(d[17]), "+f"(d[18]), "+f"(d[19]), "+f"(d[20]), "+f"(d[21]), "+f"(d[22]), "+f"(d[23]), "+f"(d[24]), "+f"(d[25]), "+f"(d[26]), "+f"(d[27]), "+f"(d[28]), "+f"(d[29]), "+f"(d[30]), "+f"(d[31]), "+f"(d[32]), "+f"(d[33]), "+f"(d[34]), "+f"(d[35]), "+f"(d[36]), "+f"(d[37]), "+f"(d[38]), "+f"(d[39]), "+f"(d[40]), "+f"(d[41]), "+f"(d[42]), "+f"(d[43]), "+f"(d[44]), "+f"(d[45]), "+f"(d[46]), "+f"(d[47]), "+f"(d[48]), "+f"(d[49]), "+f"(d[50]), "+f"(d[51]), "+f"(d[52]), "+f"(d[53]), "+f"(d[54]), "+f"(d[55]), "+f"(d[56]), "+f"(d[57]), "+f"(d[58]), "+f"(d[59]), "+f"(d[60]), "+f"(d[61]), "+f"(d[62]), "+f"(d[63])
    : "r"(a0), "r"(a1), "r"(a2), "r"(a3), "r"(descB), "r"(scaleD));
}
__device__ __forceinline__ void wgmma_conv_n96(float (&d)[48], uint32_t a0, uint32_t a1, uint32_t a2, uint32_t a3, uint32_t descB, int scaleD) {
  asm volatile("{\n.reg .pred p;\n.reg .b64 db;\nmov.b64 db, {%52, 0x00000008};\nsetp.ne.b32 p, %53, 0;\n"
    "wgmma.mma_async.sync.aligned.m64n96k16.f32.bf16.bf16 "
    "{%0, %1, %2, %3, %4, %5, %6, %7, %8, %9, %10, %11, %12, %13, %14, %15, %16, %17, %18, %19, %20, %21, %22, %23, %24, %25, %26, %27, %28, %29, %30, %31, %32, %33, %34, %35, %36, %37, %38, %39, %40, %41, %42, %43, %44, %45, %46, %47}, "
    "{%48, %49, %50, %51}, db, p, 1, 1, 0;\n}\n"
    : "+f"(d[0]), "+f"(d[1]), "+f"(d[2]), "+f"(d[3]), "+f"(d[4]), "+f"(d[5]), "+f"(d[6]), "+f"(d[7]), "+f"(d[8]), "+f"(d[9]), "+f"(d[10]), "+f"(d[11]), "+f"(d[12]), "+f"(d[13]), "+f"(d[14]), "+f"(d[15]), "+f"(d[16]), "+f"(d[17]), "+f"(d[18]), "+f"(d[19]), "+f"(d[20]), "+f"(d[21]), "+f"(d[22]), "+f"(d[23]), "+f"(d[24]), "+f"(d[25]), "+f"(d[26]), "+f"(d[27]), "+f"(d[28]), "+f"(d[29]), "+f"(d[30]), "+f"(d[31]), "+f"(d[32]), "+f"(d[33]), "+f"(d[34]), "+f"(d[35]), "+f"(d[36]), "+f"(d[37]), "+f"(d[38]), "+f"(d[39]), "+f"(d[40]), "+f"(d[41]), "+f"(d[42]), "+f"(d[43]), "+f"(d[44]), "+f"(d[45]), "+f"(d[46]), "+f"(d[47])
    : "r"(a0), "r"(a1), "r"(a2), "r"(a3), "r"(descB), "r"(scaleD));
}
__device__ __forceinline__ void wgmma_conv_n64(float (&d)[32], uint32_t a0, uint32_t a1, uint32_t a2, uint32_t a3, uint32_t descB, int scaleD) {
  asm volatile("{\n.reg .pred p;\n.reg .b64 db;\nmov.b64 db, {%36, 0x00000008};\nsetp.ne.b32 p, %37, 0;\n"
    "wgmma.mma_async.sync.aligned.m64n64k16.f32.bf16.bf16 "
    "{%0, %1, %2, %3, %4, %5, %6, %7, %8, %9, %10, %11, %12, %13, %14, %15, %16, %17, %18, %19, %20, %21, %22, %23, %24, %25, %26, %27, %28, %29, %30, %31}, "
    "{%32, %33, %34, %35}, db, p, 1, 1, 0;\n}\n"
    : "+f"(d[0]), "+f"(d[1]), "+f"(d[2]), "+f"(d[3]), "+f"(d[4]), "+f"(d[5]), "+f"(d[6]), "+f"(d[7]), "+f"(d[8]), "+f"(d[9]), "+f"(d[10]), "+f"(d[11]), "+f"(d[12]), "+f"(d[13]), "+f"(d[14]), "+f"(d[15]), "+f"(d[16]), "+f"(d[17]), "+f"(d[18]), "+f"(d[19]), "+f"(d[20]), "+f"(d[21]), "+f"(d[22]), "+f"(d[23]), "+f"(d[24]), "+f"(d[25]), "+f"(d[26]), "+f"(d[27]), "+f"(d[28]), "+f"(d[29]), "+f"(d[30]), "+f"(d[31])
    : "r"(a0), "r"(a1), "r"(a2), "r"(a3), "r"(descB), "r"(scaleD));
}
__device__ __forceinline__ void wgmma_conv_n32(float (&d)[16], uint32_t a0, uint32_t a1, uint32_t a2, uint32_t a3, uint32_t descB, int scaleD) {
  asm volatile("{\n.reg .pred p;\n.reg .b64 db;\nmov.b64 db, {%20, 0x00000008};\nsetp.ne.b32 p, %21, 0;\n"
    "wgmma.mma_async.sync.aligned.m64n32k16.f32.bf16.bf16 "
    "{%0, %1, %2, %3, %4, %5, %6, %7, %8, %9, %10, %11, %12, %13, %14, %15}, "
    "{%16, %17, %18, %19}, db, p, 1, 1, 0;\n}\n"
    : "+f"(d[0]), "+f"(d[1]), "+f"(d[2]), "+f"(d[3]), "+f"(d[4]), "+f"(d[5]), "+f"(d[6]), "+f"(d[7]), "+f"(d[8]), "+f"(d[9]), "+f"(d[10]), "+f"(d[11]), "+f"(d[12]), "+f"(d[13]), "+f"(d[14]), "+f"(d[15])
    : "r"(a0), "r"(a1), "r"(a2), "r"(a3), "r"(descB), "r"(scaleD));
}

__device__ __forceinline__ void epoch_publish(uint32_t slot_addr) {
  uint32_t e;
  asm volatile("ld.relaxed.gpu.global.u32 %0, [%1];" : "=r"(e) : "l"(&g_epoch) : "memory");
  e += 1;
  asm volatile("st.volatile.shared.u32 [%0], %1;" ::"r"(slot_addr), "r"(e) : "memory");
  const uint32_t old = atomicAdd(&g_done, 1);
  if (old == NCTA - 1) {
    g_done = 0;
    asm volatile("st.relaxed.gpu.global.u32 [%0], %1;" ::"l"(&g_epoch), "r"(e) : "memory");
  }
}
__device__ __forceinline__ uint32_t epoch_get(uint32_t slot_addr) {
  uint32_t e;
  asm volatile("{\n.reg .pred p;\nEP_LOOP:\nld.volatile.shared.u32 %0, [%1];\nsetp.eq.u32 p, %0, 0;\n@p bra EP_LOOP;\n}"
               : "=r"(e) : "r"(slot_addr) : "memory");
  return e;
}

#define G1_LEAD 4
__device__ __forceinline__ uint32_t g1_hpiece(const float (&acc)[32], int idx, float r0, float r1) {
  const int a = (idx >> 1) * 4 + (idx & 1) * 2;
  const float r = (idx & 1) ? r1 : r0;
  uint32_t g, u, h;
  asm volatile("cvt.rn.relu.bf16x2.f32 %0, %1, %2;" : "=r"(g) : "f"(acc[a + 1] * r), "f"(acc[a] * r));
  asm volatile("cvt.rn.bf16x2.f32 %0, %1, %2;" : "=r"(u) : "f"(acc[a + 17] * r), "f"(acc[a + 16] * r));
  asm volatile("mul.rn.bf16x2 %0, %1, %2;" : "=r"(h) : "r"(g), "r"(u));
  return h;
}

__device__ __forceinline__ void mma_gram(float (&c)[4], const uint32_t (&a)[4], uint32_t b0, uint32_t b1) {
  asm volatile("mma.sync.aligned.m16n8k16.row.col.f32.bf16.bf16.f32 {%0, %1, %2, %3}, {%4, %5, %6, %7}, {%8, %9}, {%0, %1, %2, %3};"
               : "+f"(c[0]), "+f"(c[1]), "+f"(c[2]), "+f"(c[3])
               : "r"(a[0]), "r"(a[1]), "r"(a[2]), "r"(a[3]), "r"(b0), "r"(b1));
}

__device__ __forceinline__ void g1_consumer(uint32_t sb, uint32_t bars, int mblk, int jj, int nu) {
  const int tid = threadIdx.x;
  const int wg = tid >> 7, warp = (tid >> 5) & 3, lane = tid & 31;
  uint32_t xr[36][4];
  float cs[2][4], g0[2][4], g1[2][4];
#pragma unroll
  for (int i = 0; i < 2; i++)
#pragma unroll
    for (int j = 0; j < 4; j++) cs[i][j] = g0[i][j] = g1[i][j] = 0.f;
  const int lrow = wg * 64 + warp * 16 + (lane & 7) + ((lane >> 3) & 1) * 8;
  {
    const uint32_t xrow = sb + G1_X_OFF + lrow * 128;
#pragma unroll
    for (int kb = 0; kb < 9; kb++) {
      mbar_wait(bars + (B_XFULL + kb) * 8, 0);
      if (kb == 0 && tid == 0) PROF(3);
      if (kb == 8 && tid == 0) PROF(8);
#pragma unroll
      for (int kk = 0; kk < 4; kk++) {
        const uint32_t chunk = (uint32_t)((kk * 2 + (lane >> 4)) ^ (lrow & 7));
        uint32_t (&a)[4] = xr[kb * 4 + kk];
        ldsm_x4(a, xrow + kb * 16384 + chunk * 16);
        mma_ones(cs[kk & 1], a);
        mma_gram(g0[kk & 1], a, a[0], a[2]);
        mma_gram(g1[kk & 1], a, a[1], a[3]);
      }
    }
  }
  const float mean0 = (cs[0][0] + cs[1][0]) * (1.0f / D_);
  const float mean1 = (cs[0][2] + cs[1][2]) * (1.0f / D_);
  const uint32_t mp0 = pack_bf2(mean0, mean0), mp1 = pack_bf2(mean1, mean1);
  cluster_wait();
  if (lane < 2) mbar_arrive_cta(bars + B_XFREE * 8, lane);
  float r0, r1;
  {
    const int g = lane >> 2;
    const float d0 = (g & 1) ? g0[0][1] + g0[1][1] : g0[0][0] + g0[1][0];
    const float d1 = (g & 1) ? g1[0][3] + g1[1][3] : g1[0][2] + g1[1][2];
    const float q0 = __shfl_sync(0xffffffffu, d0, 4 * g + (g >> 1)), q1 = __shfl_sync(0xffffffffu, d1, 4 * g + (g >> 1));
    const float v0 = fmaxf(q0 * (1.0f / D_) - mean0 * mean0, 0.f);
    const float v1 = fmaxf(q1 * (1.0f / D_) - mean1 * mean1, 0.f);
    r0 = 1.0f / bf_round(sqrtf(bf_round(bf_round(v0) + 1e-5f)));
    r1 = 1.0f / bf_round(sqrtf(bf_round(bf_round(v1) + 1e-5f)));
    if (jj == 0 && (lane & 3) == 0) {
      const int grow = mblk * 128 + wg * 64 + warp * 16 + g;
      g_stats[grow] = make_float2(bf_lo(mp0), r0);
      g_stats[grow + 8] = make_float2(bf_lo(mp1), r1);
    }
  }
#pragma unroll
  for (int i = 0; i < 36; i++) {
    xr[i][0] = bf2_sub(xr[i][0], mp0);
    xr[i][1] = bf2_sub(xr[i][1], mp1);
    xr[i][2] = bf2_sub(xr[i][2], mp0);
    xr[i][3] = bf2_sub(xr[i][3], mp1);
  }
  if (tid == 0) PROF(1);

  const uint64_t descb = (uint64_t)desc_lo(sb, 12288) | (0x80000020ull << 32);
  const uint32_t st_addr0 = sb + G1_HST_OFF + lrow * 64 + (((uint32_t)((lane >> 4) ^ ((lrow >> 1) & 3))) << 4);
  const bool rel = (warp == 0 && lane < 2);
  float accA[32], accB[32];
#pragma unroll
  for (int i = 0; i < 32; i++) accA[i] = 0.f;

  wg_fence();
#pragma unroll
  for (int s = 0; s < 3; s++) {
    mbar_wait(bars + (B_FULL + s) * 8, 0);
    const uint64_t d0 = descb + (uint64_t)(s * (G1_STAGE_BYTES >> 4));
#pragma unroll
    for (int kk = 0; kk < 12; kk++)
      wgmma_rs_n64_tb64(accA, xr[s * 12 + kk][0], xr[s * 12 + kk][1], xr[s * 12 + kk][2], xr[s * 12 + kk][3], d0 + kk * 64,
                        (s | kk) != 0);
  }
  wg_commit();
#pragma unroll
  for (int i = 0; i < 32; i++) accB[i] = 0.f;
  int st = 3;

#define G1_STEP(CUR, PREV, U, MMA)                                                                  \
  {                                                                                                 \
    uint64_t d0 = 0;                                                                                \
    if (MMA) {                                                                                      \
      const int slot = st & 7;                                                                      \
      mbar_wait(bars + (B_FULL + slot) * 8, (st >> 3) & 1);                                         \
      wg_fence();                                                                                   \
      d0 = descb + (uint64_t)(slot * (G1_STAGE_BYTES >> 4));                                                  \
      _Pragma("unroll") for (int kk = 0; kk < G1_LEAD; kk++)                                        \
        wgmma_rs_n64_tb64(CUR, xr[kk][0], xr[kk][1], xr[kk][2], xr[kk][3], d0 + kk * 64, kk != 0);  \
      wg_commit();                                                                                  \
      wg_wait<1>();                                                                                 \
    } else {                                                                                        \
      wg_wait<0>();                                                                                 \
    }                                                                                               \
    if (rel) {                                                                                      \
      mbar_arrive_cta(bars + (B_EMPTY + ((st - 3) & 7)) * 8, lane);                                 \
      mbar_arrive_cta(bars + (B_EMPTY + ((st - 2) & 7)) * 8, lane);                                 \
      mbar_arrive_cta(bars + (B_EMPTY + ((st - 1) & 7)) * 8, lane);                                 \
    }                                                                                               \
    const int pu = (U) - 1;                                                                         \
    if (pu >= 2) mbar_wait(bars + (B_HEMPTY + (pu & 1)) * 8, ((pu >> 1) - 1) & 1);                  \
    const uint32_t hb = st_addr0 + (pu & 1) * 8192;                                                 \
    uint32_t h[4];                                                                                  \
    _Pragma("unroll") for (int e = 0; e < 9; e++) {                                                 \
      const int kk = G1_LEAD + e;                                                                   \
      if (MMA && kk < 12) wgmma_rs_n64_tb64(CUR, xr[kk][0], xr[kk][1], xr[kk][2], xr[kk][3], d0 + kk * 64, 1);  \
      if (e < 8) h[e & 3] = g1_hpiece(PREV, e, r0, r1);                                             \
      if (e == 3) stsm_x4(hb, h[0], h[1], h[2], h[3]);                                              \
      if (e == 7) stsm_x4(hb ^ 32, h[0], h[1], h[2], h[3]);                                         \
      if (e == 8) { fence_async_smem(); mbar_arrive(bars + (B_HFULL + (pu & 1)) * 8); }             \
    }                                                                                               \
    if (MMA) { _Pragma("unroll") for (int kk = G1_LEAD + 9; kk < 12; kk++)                          \
      wgmma_rs_n64_tb64(CUR, xr[kk][0], xr[kk][1], xr[kk][2], xr[kk][3], d0 + kk * 64, 1); }        \
    if (MMA) {                                                                                      \
      _Pragma("unroll") for (int s = 1; s < 3; s++) {                                               \
        const int slot = (st + s) & 7;                                                              \
        mbar_wait(bars + (B_FULL + slot) * 8, ((st + s) >> 3) & 1);                                 \
        const uint64_t d1 = descb + (uint64_t)(slot * (G1_STAGE_BYTES >> 4));                                   \
        _Pragma("unroll") for (int kk = 0; kk < 12; kk++)                                           \
          wgmma_rs_n64_tb64(CUR, xr[s * 12 + kk][0], xr[s * 12 + kk][1], xr[s * 12 + kk][2],          \
                          xr[s * 12 + kk][3], d1 + kk * 64, 1);                                     \
      }                                                                                             \
      wg_commit();                                                                                  \
      st += 3;                                                                                      \
    }                                                                                               \
  }

  int u = 1;
  for (; u + 1 < nu; u += 2) {
    G1_STEP(accB, accA, u, true)
    G1_STEP(accA, accB, u + 1, true)
  }
  if (u < nu) {
    G1_STEP(accB, accA, u, true)
    G1_STEP(accA, accB, u + 1, false)
  } else {
    G1_STEP(accB, accA, u, false)
  }
#undef G1_STEP
  if (tid == 0) PROF(2);
}

__device__ __forceinline__ void g1_load_x(const Params& p, uint32_t sb, uint32_t bars, int mblk) {
  for (int kb = 0; kb < 9; kb++) {
    mbar_expect_tx(bars + (B_XFULL + kb) * 8, 16384);
    tma_load_2d(sb + G1_X_OFF + kb * 16384, &p.m_x, kb * 64, mblk * 128, bars + (B_XFULL + kb) * 8);
  }
}

__device__ __forceinline__ void g1_producer(const Params& p, uint32_t sb, uint32_t bars, int f0, int nu, uint32_t crank) {
  const CUtensorMap* wm = crank ? &p.m_wu : &p.m_wg;
  const int nst = nu * 3;
  int s = 0, f = f0;
  for (int st = 0; st < nst; st++) {
    const int slot = st & 7;
    if (st == 2) mbar_wait(bars + B_XFREE * 8, 0);
    if (st >= 8) mbar_wait(bars + (B_EMPTY + slot) * 8, ((st >> 3) - 1) & 1);
    mbar_expect_tx(bars + (B_FULL + slot) * 8, G1_STAGE_BYTES);
    tma_load_2d_mc(sb + slot * G1_STAGE_BYTES + crank * 12288, wm, f, s * 192, bars + (B_FULL + slot) * 8);
    if (++s == 3) { s = 0; f += 32; }
  }
}

__device__ __forceinline__ void g1_store(const Params& p, uint32_t sb, uint32_t bars, int mblk, int jj, int f0, int nu, uint32_t epoch, int par) {
  uint32_t* prog = &g_hprog[mblk * 16 + jj * 2 + par];
  for (int u = par; u < nu; u += 2) {
    mbar_wait(bars + (B_HFULL + par) * 8, (u >> 1) & 1);
    if (u == 20) PROF(9);
    tma_store_2d(&p.m_h, sb + G1_HST_OFF + par * 8192, f0 + u * 32, mblk * 128);
    bulk_commit();
    bulk_wait_read0();
    mbar_arrive(bars + (B_HEMPTY + par) * 8);
    if (u == 20) PROF(10);
    bulk_wait0();
    if (u == 20) PROF(11);
    st_release(prog, epoch * 64 + (u >> 1) + 1);
    if (u == 20) PROF(12);
  }
}

__device__ __forceinline__ void g2_producer_a(const Params& p, uint32_t sb, uint32_t bars, int mblk, uint32_t epoch, int par) {
  const int lane = threadIdx.x & 31;
  const uint32_t ebase = epoch * 64;
  const uint32_t* prog = &g_hprog[mblk * 16 + (lane < 10 ? lane : 0)];
  uint32_t seen = 0;
  int slot = par, round = 0, i0 = 0, j0 = par;
  mbar_wait(bars + B_PADONE * 8, 0);
  for (int q = par; q < 144; q += 2) {
    uint32_t n = 0;
    while (__shfl_sync(0xffffffffu, seen, j0 * 2 + (i0 & 1)) <= (uint32_t)(i0 >> 1)) {
      const uint32_t v = ld_relaxed(prog) - ebase;
      if (v <= 64u) seen = v;
      trap_if(++n > SPIN_LIMIT);
    }
    if (q == 100 && lane == 0) PROF(9);
    if (q == 4 + par) mbar_wait(bars + B_PFREE * 8, 0);
    if (round > 0) mbar_wait(bars + (B_EMPTY + slot) * 8, (round - 1) & 1);
    if (lane == 0) {
      if (q == 100) PROF(10);
      if (q == 143) PROF(5);
      const uint32_t full = bars + (B_FULL + slot) * 8;
      mbar_expect_tx(full, G2_STAGE_BYTES);
      tma_load_2d(sb + slot * G2_STAGE_BYTES, &p.m_h, j0 * G1_FSPAN + i0 * 32, mblk * 128, full);
      if (q == 143) PROF(6);
    }
    j0 += 2;
    if (j0 >= 5) { j0 -= 5; i0++; }
    slot += 2;
    if (slot >= G2_STAGES) { slot -= G2_STAGES; round++; }
  }
}

__device__ __forceinline__ void g2_producer_b(const Params& p, uint32_t sb, uint32_t bars, int mblk, int ntile, uint32_t crank, uint32_t epoch) {
  int slot = crank, round = 0, i0 = 0, j0 = crank;
  mbar_wait(bars + B_PADONE * 8, 0);
  for (int q = crank; q < 144; q += 2) {
    if (q == 4 + (int)crank) { mbar_wait(bars + B_PFREE * 8, 0); PROF(27); }
    if (round > 0) mbar_wait(bars + (B_EMPTY + slot) * 8, (round - 1) & 1);
    tma_load_3d_mc(sb + slot * G2_STAGE_BYTES + 8192, &p.m_wd, 0, j0 * G1_FSPAN + i0 * 32, ntile * 3, bars + (B_FULL + slot) * 8);
    j0 += 2;
    if (j0 >= 5) { j0 -= 5; i0++; }
    slot += 2;
    if (slot >= G2_STAGES) { slot -= G2_STAGES; round++; }
  }
  PROF(28);
  spin_ge(&g_ycnt[ntile * 8], epoch * 192u);
  PROF(29);
  mbar_wait(bars + (B_EMPTY + 4) * 8, 13 & 1);
  mbar_wait(bars + (B_EMPTY + 5) * 8, 13 & 1);
  mbar_expect_tx(bars + B_YFULL * 8, 24576);
  tma_load_2d(sb + G2_Y_OFF, &p.m_y, mblk * 128, ntile * 192, bars + B_YFULL * 8);
  mbar_wait(bars + (B_EMPTY + 6) * 8, 13 & 1);
  mbar_expect_tx(bars + (B_YFULL + 1) * 8, 24576);
  tma_load_2d(sb + G2_Y_OFF + 24576, &p.m_y, mblk * 128 + 64, ntile * 192, bars + (B_YFULL + 1) * 8);
  PROF(7);
}

__device__ __forceinline__ void g2_consumer(const Params& p, uint32_t sb, uint32_t bars, int mblk, int ntile) {
  const int tid = threadIdx.x;
  const int wg = __shfl_sync(0xffffffffu, tid >> 7, 0), warp = (tid >> 5) & 3, lane = tid & 31;
  float acc[96];
#pragma unroll
  for (int i = 0; i < 96; i++) acc[i] = 0.f;
  const uint32_t da0 = desc_lo(sb + wg * 4096, 16);
  const uint32_t db0 = desc_lo(sb + 8192, 4096);
  const bool rel = (warp == 0 && lane < 2);
  const int r16 = wg * 64 + warp * 16;
  const int grow = mblk * 128 + r16 + (lane >> 2);
  uint32_t xv[12][4];
  const __nv_bfloat16* xp = p.x + (size_t)grow * D_ + ntile * 192 + (lane & 3) * 2;
  float2 s0, s1;
  int slot = 0, ph = 0, pslot = 0;
#define G2_STAGE(EXTRA)                                                                             \
    {                                                                                               \
      CLK_BEGIN(wfull);                                                                             \
      mbar_wait(bars + (B_FULL + slot) * 8, ph);                                                    \
      CLK_END(wfull);                                                                               \
      if (st == 0 && tid == 0) PROF(1);                                                             \
      wg_fence();                                                                                   \
      const uint32_t so = slot * (G2_STAGE_BYTES >> 4);                                             \
      _Pragma("unroll") for (int kk = 0; kk < 2; kk++)                                              \
        wgmma_ss_n192_tb(acc, da0 + so + kk * 2, db0 + so + kk * 128, 1);                           \
      wg_commit();                                                                                  \
      EXTRA                                                                                         \
    }
#define G2_RELEASE()                                                                                \
    wg_wait<1>();                                                                                   \
    if (st > 0 && rel) mbar_arrive_cta(bars + (B_EMPTY + pslot) * 8, lane);                         \
    pslot = slot;                                                                                   \
    if (++slot == G2_STAGES) { slot = 0; ph ^= 1; }
#pragma unroll
  for (int st = 0; st < 12; st++) {
    G2_STAGE(_Pragma("unroll") for (int q = 0; q < 4; q++)
               asm volatile("ld.global.nc.u32 %0, [%1];" : "=r"(xv[st][q]) : "l"(xp + (q & 1) * 8 * D_ + st * 16 + (q >> 1) * 8));)
    G2_RELEASE()
  }
  for (int st = 12; st < 143; st++) {
    G2_STAGE()
    G2_RELEASE()
  }
  {
    const int st = 143;
    G2_STAGE()
  }
#undef G2_STAGE
#undef G2_RELEASE
  if (tid == 0) PROF(16);
  asm volatile("ld.global.cg.v2.f32 {%0, %1}, [%2];" : "=f"(s0.x), "=f"(s0.y) : "l"(&g_stats[grow]) : "memory");
  asm volatile("ld.global.cg.v2.f32 {%0, %1}, [%2];" : "=f"(s1.x), "=f"(s1.y) : "l"(&g_stats[grow + 8]) : "memory");
  const int lrow = r16 + (lane & 7) + ((lane >> 3) & 1) * 8;
  const int tloc = r16 & 63;
  const uint32_t ybase = sb + G2_Y_OFF + wg * 24576;
  const uint32_t mp0 = pack_bf2(s0.x, s0.x), mp1 = pack_bf2(s1.x, s1.x);
  uint32_t xn[12][4];
#pragma unroll
  for (int i2 = 0; i2 < 12; i2++)
#pragma unroll
    for (int q = 0; q < 4; q++) {
      const uint32_t dd = bf2_sub(xv[i2][q], (q & 1) ? mp1 : mp0);
      const float r = (q & 1) ? s1.y : s0.y;
      asm volatile("cvt.rn.bf16x2.f32 %0, %1, %2;" : "=r"(xn[i2][q]) : "f"(bf_hi(dd) * r), "f"(bf_lo(dd) * r));
    }
  if (tid == 0) PROF(17);
  mbar_wait(bars + (B_YFULL + wg) * 8, 0);
  if (tid == 0) PROF(18);
#pragma unroll
  for (int i2 = 0; i2 < 12; i2++) {
    uint32_t yv[4];
    const int drow = i2 * 16 + (lane & 7) + (lane >> 4) * 8;
    const int tch = (tloc >> 3) + ((lane >> 3) & 1);
    ldsm_x4_t(yv, ybase + drow * 128 + ((tch ^ (drow & 7)) << 4));
#pragma unroll
    for (int q = 0; q < 4; q++) xv[i2][q] = bf2_add(xv[i2][q], bf2_mul(xn[i2][q], yv[q]));
  }
  if (tid == 0) PROF(19);
  mbar_wait(bars + (B_EMPTY + 6) * 8, 13 & 1);
  mbar_wait(bars + (B_EMPTY + 7) * 8, 13 & 1);
  mbar_wait(bars + (B_EMPTY + 8) * 8, 13 & 1);
  wg_wait<0>();
  if (tid == 0) PROF(2);
  const uint32_t obase = sb + G2_O_OFF + lrow * 128;
#pragma unroll
  for (int i2 = 0; i2 < 12; i2++) {
    uint32_t o[4];
#pragma unroll
    for (int q = 0; q < 4; q++) {
      const int ai = (i2 * 2 + (q >> 1)) * 4 + (q & 1) * 2;
      o[q] = bf2_add(xv[i2][q], pack_bf2(acc[ai], acc[ai + 1]));
    }
    stsm_x4(obase + (i2 >> 2) * 16384 + ((((i2 & 3) * 2 + (lane >> 4)) ^ (lrow & 7)) << 4), o[0], o[1], o[2], o[3]);
  }
  if (tid == 0) PROF(20);
  named_sync(1 + wg, 128);
  {
    const int t = tid & 127;
    uint8_t* gout = reinterpret_cast<uint8_t*>(p.out) + (size_t)(mblk * 128 + wg * 64) * (D_ * 2) + ntile * 384;
#pragma unroll
    for (int i = 0; i < 12; i++) {
      const int ci = i * 128 + t, row = ci / 24, cc = ci - row * 24;
      uint4 v;
      asm volatile("ld.shared.v4.u32 {%0, %1, %2, %3}, [%4];" : "=r"(v.x), "=r"(v.y), "=r"(v.z), "=r"(v.w)
                   : "r"(sb + G2_O_OFF + (cc >> 3) * 16384 + (wg * 64 + row) * 128 + (((cc & 7) ^ (row & 7)) << 4)) : "memory");
      *reinterpret_cast<uint4*>(gout + row * (D_ * 2) + cc * 16) = v;
    }
  }
  if (tid == 0) PROF(3);
}

#define UCNT_SIGNAL red_release_add
#define NCHG2 6
constexpr int NCH_G1 = 2;
constexpr int NCH_G2 = NCHG2;
constexpr int NCH_SP = (D_ - 80 * NCH_G1 - 48 * NCH_G2) / 4;
static_assert(80 * NCH_G1 + 48 * NCH_G2 + 4 * NCH_SP == D_, "channel split");

__device__ __forceinline__ void conv_channels_of(int cid, uint32_t crank, int& ch0, int& nch) {
  const int cta = cid * 2 + crank;
  if (cid < G1_CLUSTERS) { ch0 = cta * NCH_G1; nch = NCH_G1; }
  else if (cid < G1_CLUSTERS + G2_CLUSTERS) { ch0 = 80 * NCH_G1 + (cta - 80) * NCH_G2; nch = NCH_G2; }
  else { ch0 = 80 * NCH_G1 + 48 * NCH_G2 + (cta - 128) * NCH_SP; nch = NCH_SP; }
}
__device__ __forceinline__ uint32_t lds32(uint32_t a) {
  uint32_t v;
  asm volatile("ld.shared.u32 %0, [%1];" : "=r"(v) : "r"(a) : "memory");
  return v;
}
__device__ __forceinline__ uint32_t dup(uint32_t v) {
  uint32_t d;
  asm volatile("mov.b32 %0, %1;" : "=r"(d) : "r"(v));
  return d;
}
__device__ __forceinline__ uint32_t pin(uint32_t v, uint32_t z) {
  uint32_t d;
  asm volatile("xor.b32 %0, %1, %2;" : "=r"(d) : "r"(v), "r"(z));
  return d;
}
__device__ __forceinline__ uint32_t conv_rsum(const float (&t)[8], uint32_t uw, uint32_t dpk) {
  uint32_t o;
  asm volatile("{\n.reg .f32 a, b, c, d;\n.reg .b32 y, u;\n"
               "add.f32 a, %1, %3;\nadd.f32 b, %5, %7;\nadd.f32 a, a, b;\n"
               "add.f32 c, %2, %4;\nadd.f32 d, %6, %8;\nadd.f32 c, c, d;\n"
               "cvt.rn.bf16x2.f32 y, c, a;\n"
               "prmt.b32 u, %9, 0, 0x1032;\n"
               "mul.rn.bf16x2 u, u, %10;\n"
               "add.rn.bf16x2 %0, y, u;\n}"
               : "=r"(o)
               : "f"(t[0]), "f"(t[1]), "f"(t[2]), "f"(t[3]), "f"(t[4]), "f"(t[5]), "f"(t[6]), "f"(t[7]), "r"(uw), "r"(dpk));
  return o;
}
__device__ __forceinline__ float dupf(float v) {
  float d;
  asm volatile("mov.b32 %0, %1;" : "=f"(d) : "f"(v));
  return d;
}
__device__ __forceinline__ float lds_f32(uint32_t a) {
  float v;
  asm volatile("ld.shared.f32 %0, [%1];" : "=f"(v) : "r"(a) : "memory");
  return v;
}
__device__ __forceinline__ uint4 lds128(uint32_t a) {
  uint4 v;
  asm volatile("ld.shared.v4.u32 {%0, %1, %2, %3}, [%4];" : "=r"(v.x), "=r"(v.y), "=r"(v.z), "=r"(v.w) : "r"(a) : "memory");
  return v;
}
__device__ __forceinline__ void sts128(uint32_t a, uint32_t x, uint32_t y, uint32_t z, uint32_t w) {
  asm volatile("st.shared.v4.u32 [%0], {%1, %2, %3, %4};" ::"r"(a), "r"(x), "r"(y), "r"(z), "r"(w) : "memory");
}
__device__ __forceinline__ void sts128f(uint32_t a, float x, float y, float z, float w) {
  asm volatile("st.shared.v4.f32 [%0], {%1, %2, %3, %4};" ::"r"(a), "f"(x), "f"(y), "f"(z), "f"(w) : "memory");
}
__device__ __forceinline__ float4 lds128f(uint32_t a) {
  float4 v;
  asm volatile("ld.shared.v4.f32 {%0, %1, %2, %3}, [%4];" : "=f"(v.x), "=f"(v.y), "=f"(v.z), "=f"(v.w) : "r"(a) : "memory");
  return v;
}
__device__ __forceinline__ void stsm_x4_t(uint32_t addr, uint32_t r0, uint32_t r1, uint32_t r2, uint32_t r3) {
  asm volatile("stmatrix.sync.aligned.m8n8.x4.trans.shared.b16 [%0], {%1, %2, %3, %4};"
               ::"r"(addr), "r"(r0), "r"(r1), "r"(r2), "r"(r3) : "memory");
}
__device__ __forceinline__ void sts64f(uint32_t a, float x, float y) {
  asm volatile("st.shared.v2.f32 [%0], {%1, %2};" ::"r"(a), "f"(x), "f"(y) : "memory");
}

__device__ __forceinline__ void prep_load(const Params& p, uint32_t sb, uint32_t bars, int mblk, int ntile) {
  for (int g = 0; g < 3; g++) {
    const uint32_t bar = bars + (B_KVFULL + g) * 8;
    mbar_expect_tx(bar, 132 * 128 + 16384);
    tma_load_2d(sb + PA_K_OFF + g * PA_K_BOX, &p.m_k, ntile * 192 + g * 64, mblk * 128 - 4, bar);
    tma_load_2d(sb + PA_V_OFF + g * 16384, &p.m_v, ntile * 192 + g * 64, mblk * 128, bar);
  }
}

__device__ __forceinline__ void prep_compute(const Params& p, uint32_t sb, uint32_t bars, int mblk, int ntile, uint32_t epoch) {
  const int tid = threadIdx.x, warp = tid >> 5, lane = tid & 31;
  uint4 sw[2];
#pragma unroll
  for (int i = 0; i < 2; i++)
    sw[i] = __ldg(reinterpret_cast<const uint4*>(p.shift_k + (ntile * 192 + ((warp + 12 * i) >> 3) * 64 + lane * 2) * 4));
#pragma unroll
  for (int i = 0; i < 2; i++) {
    const int task = warp + 12 * i, blk16 = task & 7, g = task >> 3;
    mbar_wait(bars + (B_KVFULL + g) * 8, 0);
    if (i == 0 && tid == 0) PROF(13);
    const uint32_t w0 = __byte_perm(sw[i].x, sw[i].z, 0x5410), w1 = __byte_perm(sw[i].x, sw[i].z, 0x7632);
    const uint32_t w2 = __byte_perm(sw[i].y, sw[i].w, 0x5410), w3 = __byte_perm(sw[i].y, sw[i].w, 0x7632);
    const uint32_t ka = sb + PA_K_OFF + g * PA_K_BOX + (blk16 * 16 + 1) * 128 + lane * 4;
    const uint32_t va = sb + PA_V_OFF + g * 16384 + (blk16 * 16) * 128 + lane * 4;
    uint32_t kk[19], kv[16];
#pragma unroll
    for (int r = 0; r < 19; r++) kk[r] = lds32(ka + r * 128);
#pragma unroll
    for (int r = 0; r < 16; r++) kv[r] = lds32(va + r * 128);
#pragma unroll
    for (int r = 0; r < 16; r++) {
      uint32_t a = bf2_mul(kk[r], w3);
      a = bf2_add(a, bf2_mul(kk[r + 1], w2));
      a = bf2_add(a, bf2_mul(kk[r + 2], w1));
      a = bf2_add(a, bf2_mul(kk[r + 3], w0));
      kv[r] = bf2_mul(a, kv[r]);
    }
    const int blk = 7 - blk16;
    const int row = g * 64 + lane * 2;
    const uint32_t sa = sb + PA_U_OFF + (blk >> 2) * 24576 + row * 128;
    const uint32_t c0 = (uint32_t)((blk & 3) * 2);
    uint32_t o[8];
#pragma unroll
    for (int m = 0; m < 8; m++) o[m] = __byte_perm(kv[15 - 2 * m], kv[14 - 2 * m], 0x5410);
    sts128(sa + ((c0 ^ (row & 7)) << 4), o[0], o[1], o[2], o[3]);
    sts128(sa + (((c0 + 1) ^ (row & 7)) << 4), o[4], o[5], o[6], o[7]);
#pragma unroll
    for (int m = 0; m < 8; m++) o[m] = __byte_perm(kv[15 - 2 * m], kv[14 - 2 * m], 0x7632);
    sts128(sa + 128 + ((c0 ^ ((row + 1) & 7)) << 4), o[0], o[1], o[2], o[3]);
    sts128(sa + 128 + (((c0 + 1) ^ ((row + 1) & 7)) << 4), o[4], o[5], o[6], o[7]);
  }
  if (tid == 0) PROF(13);
  fence_async_smem();
  named_sync(4, 384);
  if (tid == 32) {
    PROF(13);
    const int t0 = (127 - (mblk * 8 + 7)) * 16;
    tma_store_2d(&p.m_us, sb + PA_U_OFF, t0, ntile * 192);
    tma_store_2d(&p.m_us, sb + PA_U_OFF + 24576, t0 + 64, ntile * 192);
    bulk_commit();
    bulk_wait0();

    UCNT_SIGNAL(&g_ucnt[ntile * 8], 1);
    PROF(13);
    mbar_arrive_cta(bars + B_PADONE * 8, 0);
    mbar_arrive_cta(bars + B_PADONE * 8, 1);
  }
}

__device__ __forceinline__ void wd_prefetch(const Params& p, int mblk, int ntile) {
  for (int i = 0; i < 9; i++)
    asm volatile("cp.async.bulk.prefetch.tensor.3d.L2.global [%0, {%1, %2, %3}];"
                 ::"l"(&p.m_wd), "r"(0), "r"(mblk * 288 + i * 32), "r"(ntile * 3) : "memory");
}

__device__ __forceinline__ void conv_load_k(const Params& p, uint32_t kb, uint32_t bar, int ch) {
  mbar_expect_tx(bar, 4096);
  asm volatile("cp.async.bulk.shared::cluster.global.mbarrier::complete_tx::bytes [%0], [%1], %2, [%3];"
               ::"r"(kb + 32), "l"(p.ssm_k + (size_t)ch * S_), "r"(4096), "r"(bar) : "memory");
}
__device__ __forceinline__ void conv_load_u(const Params& p, uint32_t ub, uint32_t bar, int ch) {
  mbar_expect_tx(bar, 4096);
  tma_load_4d(ub, &p.m_u, 0, 0, 0, ch, bar);
  tma_load_4d(ub + 2176, &p.m_u, 0, 0, 1, ch, bar);
}
__device__ __forceinline__ void conv_build_ko(uint32_t kb, int t) {
#pragma unroll
  for (int i = 0; i < 2; i++) {
    const int ck = t + i * 128;
    const uint4 v = lds128(kb + 32 + ck * 16);
    const uint32_t nx = (ck < 255) ? lds32(kb + 48 + ck * 16) : 0u;
    sts128(kb + 4160 + 32 + ck * 16, __byte_perm(v.x, v.y, 0x5432), __byte_perm(v.y, v.z, 0x5432),
           __byte_perm(v.z, v.w, 0x5432), __byte_perm(v.w, nx, 0x5432));
    if (ck == 0) sts128(kb + 4160 + 16, 0, 0, 0, v.x << 16);
  }
}

__device__ __forceinline__ void conv_zero_pads(uint32_t ub, uint32_t kb, int t, int ns) {
  if (t < 16 * ns) sts128(ub + (t >> 3) * 2176 + 2048 + (t & 7) * 16, 0, 0, 0, 0);
  else if (t >= 64 && t < 64 + 3 * ns) {
    const int s = (t - 64) / 3, r = (t - 64) - s * 3;
    sts128(kb + s * CV_K_BYTES + (r == 2 ? 4160 : r * 16), 0, 0, 0, 0);
  }
}

#define CONV_LOAD(F, KA, I)                                                           \
    {                                                                                 \
      uint32_t w_[17];                                                                \
      _Pragma("unroll") for (int m = 0; m < 17; m++) w_[m] = lds32((KA) + (I) * 1024 + m * 16);             \
      _Pragma("unroll") for (int j = 0; j < 8; j++) {                                 \
        F[j][0] = (j == 0) ? w_[0] : dup(w_[2 * j]);                                  \
        F[j][1] = w_[2 * j + 1]; F[j][2] = dup(w_[2 * j + 1]); F[j][3] = w_[2 * j + 2];                     \
      }                                                                               \
    }
#define CONV_QUAD(FN, ACC, F, I)                                                      \
    wg_fence();                                                                       \
    _Pragma("unroll") for (int j = 0; j < 8; j++)                                     \
      FN(ACC, F[j][0], F[j][1], F[j][2], F[j][3], dB + 32 * (I) + j, ((I) | j) != 0); \
    wg_commit();
#define CONV_STORE(SRC, T0)                                                           \
    _Pragma("unroll") for (int t = (T0); t < (T0) + 4; t++)                           \
      if (t >= 3 || t >= warp) sts128f(pw + t * 512, SRC[4 * t], SRC[4 * t + 1], SRC[4 * t + 2], SRC[4 * t + 3]);
#define CONV_SHRINK(DST, SRC, N) _Pragma("unroll") for (int i = 0; i < N; i++) DST[i] = SRC[i];
#define CONV_SHRINK_O(DST, SRC, N) _Pragma("unroll") for (int i = 0; i < N; i++) DST[i] = dupf(SRC[i]);
#define CONV_READ_U(UB)                                                               \
    {                                                                                 \
      const uint4 u0 = lds128((UB) + n * 16), u1 = lds128((UB) + 2176 + n * 16);        \
      uw[0] = u1.w; uw[1] = u1.z; uw[2] = u1.y; uw[3] = u1.x; uw[4] = u0.w; uw[5] = u0.z; uw[6] = u0.y; uw[7] = u0.x; \
    }
#define CONV_REDUCE()                                                                 \
    {                                                                                 \
      uint32_t m_[8];                                                                 \
      _Pragma("unroll") for (int i = 0; i < 4; i++) {                                 \
        const int t = 4 * warp + i;                                                   \
        const float4 p0 = lds128f(pb + t * 512 + lane * 16);                          \
        const float4 p1 = lds128f(t + 1 > 15 ? pzero : pb + 8192 + (t + 1) * 512 + lane * 16);              \
        const float4 p2 = lds128f(t + 2 > 15 ? pzero : pb + 16384 + (t + 2) * 512 + lane * 16);             \
        const float4 p3 = lds128f(t + 3 > 15 ? pzero : pb + 24576 + (t + 3) * 512 + lane * 16);             \
        m_[2 * i] = pack_bf2((p0.x + p1.x) + (p2.x + p3.x), (p0.y + p1.y) + (p2.y + p3.y));                 \
        m_[2 * i + 1] = pack_bf2((p0.z + p1.z) + (p2.z + p3.z), (p0.w + p1.w) + (p2.w + p3.w));             \
      }                                                                               \
      const uint32_t ya = yb + (127 - (32 * warp + ((lane >> 4) * 8) + (lane & 7))) * 32 + ((lane >> 3) & 1) * 16;  \
      stsm_x4_t(ya, m_[0], m_[1], m_[2], m_[3]);                                      \
      stsm_x4_t(ya - 16 * 32, m_[4], m_[5], m_[6], m_[7]);                            \
      named_sync(1 + wg, 128);                                                        \
      const uint4 y0 = lds128(yb + (127 - n) * 32), y1 = lds128(yb + (127 - n) * 32 + 16);                  \
      const uint32_t yw[8] = {y0.x, y0.y, y0.z, y0.w, y1.x, y1.y, y1.z, y1.w};        \
      uint32_t o[8];                                                                  \
      _Pragma("unroll") for (int m = 0; m < 8; m++) o[m] = bf2_add(yw[m], bf2_mul(__byte_perm(uw[m], 0, 0x1032), dpk));  \
      uint4* dst = reinterpret_cast<uint4*>(g_yT + (size_t)chp * S_ + (127 - n) * 16);                      \
      dst[0] = make_uint4(o[0], o[1], o[2], o[3]);                                    \
      dst[1] = make_uint4(o[4], o[5], o[6], o[7]);                                    \
    }
#define CONV_SETUP(PB)                                                                \
  const int tid = threadIdx.x;                                                        \
  const int wg = __shfl_sync(0xffffffffu, tid >> 7, 0), warp = __shfl_sync(0xffffffffu, (tid >> 5) & 3, 0), lane = tid & 31;  \
  const int g = lane >> 2, c4 = lane & 3;                                             \
  const uint32_t alane = (g & 1) ? (uint32_t)((128 * warp + g + 2 * c4 + 1) * 2) : (uint32_t)(4160 + (128 * warp + g + 2 * c4) * 2);  \
           \
  const uint32_t pb = (PB);                                                           \
  const uint32_t pw = pb + warp * 8192 + lane * 16;                                   \
  const uint32_t pzero = pb + 3 * 8192 + lane * 16;                                   \
  const uint32_t yb = pb + 32768;                    \
  const int n = tid & 127;                       \
  if (warp == 3) sts128(pzero, 0, 0, 0, 0);

__device__ __forceinline__ void conv_producer_side(const Params& p, uint32_t sb, uint32_t bars, int ch0, int nch, uint32_t epoch, int warp_id) {
  const int lane = threadIdx.x & 31;
  if (warp_id == 8) {
    if (lane == 0) {
      int grp = -1;
      for (int c = 0; c < nch; c++) {
        const int ch = ch0 + c, slot = c & 3;
        const int g = ch / 192;
        if (g != grp) { spin_ge(&g_ucnt[g * 8], epoch * 16u); grp = g; if (c == 0) PROF(13); }
        if (c >= 4) mbar_wait(bars + (B_CEMPTY + slot) * 8, ((c >> 2) - 1) & 1);
        conv_load_u(p, sb + CV_U_OFF + slot * CV_U_BYTES, bars + (B_UFULL + slot) * 8, ch);
      }
    }
    __syncwarp();
  } else {
    const int t = threadIdx.x - 288;
    if (t < nch)
      asm volatile("cp.async.bulk.prefetch.L2.global [%0], %1;" ::"l"(p.ssm_k + (size_t)(ch0 + t) * S_), "r"(4096) : "memory");
    if (t < 64) sts128(sb + CV_U_OFF + (t >> 3) * 2176 + 2048 + (t & 7) * 16, 0, 0, 0, 0);
    if (t < 12) {
      const int slot = t / 3, r = t - slot * 3;
      sts128(sb + CV_K_OFF + slot * CV_K_BYTES + (r == 2 ? 4160 : r * 16), 0, 0, 0, 0);
    }
    for (int c = 0; c < nch; c++) {
      const int slot = c & 3;
      const __nv_bfloat16* kp = p.ssm_k + (size_t)(ch0 + c) * S_;
      uint4 v[3];
      uint32_t nx[3];
#pragma unroll
      for (int i = 0; i < 3; i++) {
        const int ck = t + i * 96;
        if (ck < 256) {
          v[i] = __ldg(reinterpret_cast<const uint4*>(kp + ck * 8));
          nx[i] = (ck < 255) ? __ldg(reinterpret_cast<const uint32_t*>(kp + ck * 8 + 8)) : 0u;
        }
      }
      if (c >= 4) mbar_wait(bars + (B_CEMPTY + slot) * 8, ((c >> 2) - 1) & 1);
      const uint32_t kb = sb + CV_K_OFF + slot * CV_K_BYTES;
#pragma unroll
      for (int i = 0; i < 3; i++) {
        const int ck = t + i * 96;
        if (ck < 256) {
          sts128(kb + 32 + ck * 16, v[i].x, v[i].y, v[i].z, v[i].w);
          sts128(kb + 4160 + 32 + ck * 16, __byte_perm(v[i].x, v[i].y, 0x5432), __byte_perm(v[i].y, v[i].z, 0x5432),
                 __byte_perm(v[i].z, v[i].w, 0x5432), __byte_perm(v[i].w, nx[i], 0x5432));
          if (ck == 0) sts128(kb + 4160 + 16, 0, 0, 0, v[i].x << 16);
        }
      }
      mbar_arrive(bars + (B_KFULL + slot) * 8);
    }
  }
}

#define CT(i) do {} while (0)
__device__ __forceinline__ void conv_consumer_side(const Params& p, uint32_t sb, uint32_t bars, int ch0, int nch, uint32_t epoch) {
  CONV_SETUP(sb + CV_P_OFF + (threadIdx.x >> 7) * CV_P_BYTES)
  if (tid == 0) PROF(5 + 8);
  uint32_t fa[8][4], fb[8][4];
  uint32_t uw[8], dpk = 0;
  int chp = -1;
#pragma unroll
  for (int m = 0; m < 8; m++) uw[m] = 0;
  if (wg < nch) {
    mbar_wait(bars + (B_KFULL + wg) * 8, 0);
    CONV_LOAD(fa, sb + CV_K_OFF + wg * CV_K_BYTES + alane, 0)
  }
  for (int c = wg; c < nch; c += 2) {
    const int slot = c & 3, ph = (c >> 2) & 1;
    const uint32_t ka = sb + CV_K_OFF + slot * CV_K_BYTES + alane;
    const uint32_t ub = sb + CV_U_OFF + slot * CV_U_BYTES;
    const bool more = c + 2 < nch;
    const uint32_t kan = more ? sb + CV_K_OFF + ((c + 2) & 3) * CV_K_BYTES + alane : ka;
    const uint16_t dn = __ldg(reinterpret_cast<const uint16_t*>(p.ssm_D) + ch0 + c);
    float acc[64], a48[48], a32[32], a16[16];
    const uint32_t dB = desc_lo(ub, 2176);
    CT(0);
    mbar_wait(bars + (B_UFULL + slot) * 8, ph);
    CT(1);
    CONV_QUAD(wgmma_conv_n128, acc, fa, 0)
    CONV_LOAD(fb, ka, 1)
    if (chp >= 0) CONV_REDUCE()
    wg_wait<0>();
    CT(2);
    named_sync(1 + wg, 128);
    CT(3);
    CONV_SHRINK(a48, acc, 48)
    CONV_QUAD(wgmma_conv_n96, a48, fb, 1)
    CONV_LOAD(fa, ka, 2)
    CONV_STORE(acc, 12)
    wg_wait<0>();
    CT(4);
    CONV_SHRINK(a32, a48, 32)
    CONV_QUAD(wgmma_conv_n64, a32, fa, 2)
    CONV_LOAD(fb, ka, 3)
    CONV_STORE(a48, 8)
    wg_wait<0>();
    CT(5);
    CONV_SHRINK(a16, a32, 16)
    CONV_QUAD(wgmma_conv_n32, a16, fb, 3)
    CONV_STORE(a32, 4)
    if (more) mbar_wait(bars + (B_KFULL + ((c + 2) & 3)) * 8, ((c + 2) >> 2) & 1);
    CONV_LOAD(fa, kan, 0)
    CONV_READ_U(ub)
    dpk = (uint32_t)dn * 0x10001u;
    chp = ch0 + c;
    wg_wait<0>();
    CT(6);
    CONV_STORE(a16, 0)
    named_sync(1 + wg, 128);
    mbar_arrive(bars + (B_CEMPTY + slot) * 8);
    CT(7);
    CT(8);
  }
  if (chp >= 0) CONV_REDUCE()
  named_sync(1 + wg, 128);
  if (n == 0 && wg < nch) {
    __threadfence();
    int cnt[3] = {0, 0, 0};
    for (int c = wg; c < nch; c += 2) {
      const int t = (ch0 + c) / 192;
      cnt[0] += t == 0; cnt[1] += t == 1; cnt[2] += t == 2;
    }
    if (cnt[0]) red_relaxed_add(&g_ycnt[0], cnt[0]);
    if (cnt[1]) red_relaxed_add(&g_ycnt[8], cnt[1]);
    if (cnt[2]) red_relaxed_add(&g_ycnt[16], cnt[2]);
  }
  if (n < 2) mbar_arrive_cta(bars + B_PFREE * 8, n);
  if (tid == 0) PROF(6 + 8);
}

__device__ __forceinline__ void* dyn_smem_base() {
  extern __shared__ uint8_t smem_raw[];
  return smem_raw;
}
__device__ __forceinline__ int g1_conv_slot(int nu) { return (nu * 3 - 8) & 7; }
__device__ __forceinline__ void g1_conv_loads(const Params& p, uint32_t sb, uint32_t bars, int nu, int ch0, uint32_t epoch) {
  const int x = g1_conv_slot(nu);
  for (int w = 0; w < 2; w++) {
    spin_ge(&g_ucnt[((ch0 + w) / 192) * 8], epoch * 16u);
    conv_load_u(p, sb + G1_CU_OFF + w * CV_U_BYTES, bars + (B_UFULL + w) * 8, ch0 + w);
  }
  mbar_wait(bars + (B_EMPTY + x) * 8, ((nu * 3 - 8) >> 3) & 1);
  for (int w = 0; w < 2; w++)
    conv_load_k(p, sb + x * G1_STAGE_BYTES + w * CV_K_BYTES, bars + (B_KRAW + w) * 8, ch0 + w);
}
__device__ __forceinline__ void g1_conv(const Params& p) {
  uint32_t cta, sraw;
  asm volatile("mov.u32 %0, %%ctaid.x;" : "=r"(cta));
  asm volatile("{\n.reg .u64 t;\ncvta.to.shared.u64 t, %1;\ncvt.u32.u64 %0, t;\n}" : "=r"(sraw) : "l"(dyn_smem_base()));
  const uint32_t sb = (sraw + 1023u) & ~1023u, bars = sb + BAR_OFF;
  const int nu = (cta >> 4) == 4 ? 28 : 29, ch0 = cta * NCH_G1;
  const int x = g1_conv_slot(nu);
  if (threadIdx.x == 0) PROF(31);
  named_sync(4, 256);

  CONV_SETUP(sb + (x < 4 ? 4 * G1_STAGE_BYTES : 0) + (threadIdx.x >> 7) * CV_P_BYTES)
  const uint32_t ub = sb + G1_CU_OFF + wg * CV_U_BYTES, kb = sb + x * G1_STAGE_BYTES + wg * CV_K_BYTES;
  const int chp = ch0 + wg;
  const uint32_t dpk = (uint32_t)__ldg(reinterpret_cast<const uint16_t*>(p.ssm_D) + chp) * 0x10001u;
  conv_zero_pads(ub, kb, n, 1);
  mbar_wait(bars + (B_KRAW + wg) * 8, 0);
  conv_build_ko(kb, n);
  named_sync(1 + wg, 128);
  const uint32_t ka = kb + alane;
  const uint32_t dB = desc_lo(ub, 2176);
  uint32_t fa[8][4], fb[8][4], uw[8];
  CONV_LOAD(fa, ka, 0)
  fence_async_smem();
  named_sync(1 + wg, 128);
  mbar_wait(bars + (B_UFULL + wg) * 8, 0);

  for (uint32_t it = p.zero; it < 1; it++) {
    float acc[64], a48[48], a32[32], a16[16];
    CONV_QUAD(wgmma_conv_n128, acc, fa, 0)
    CONV_LOAD(fb, ka, 1)
    CONV_READ_U(ub)
    wg_wait<0>();
    CONV_SHRINK_O(a48, acc, 48)
    CONV_QUAD(wgmma_conv_n96, a48, fb, 1)
    CONV_LOAD(fa, ka, 2)
    CONV_STORE(acc, 12)
    wg_wait<0>();
    CONV_SHRINK_O(a32, a48, 32)
    CONV_QUAD(wgmma_conv_n64, a32, fa, 2)
    CONV_LOAD(fb, ka, 3)
    CONV_STORE(a48, 8)
    wg_wait<0>();
    CONV_SHRINK_O(a16, a32, 16)
    CONV_QUAD(wgmma_conv_n32, a16, fb, 3)
    CONV_STORE(a32, 4)
    wg_wait<0>();
    CONV_STORE(a16, 0)
  }

  named_sync(1 + wg, 128);
  CONV_REDUCE()

  named_sync(1 + wg, 128);
  if (n == 0) red_release_add(&g_ycnt[(chp / 192) * 8], 1);
  if (tid == 0) PROF(6 + 8);
}
#undef CONV_STORE
#undef CONV_SHRINK
#undef CONV_LOAD
#undef CONV_QUAD
#undef CONV_REDUCE
#undef CONV_READ_U
#undef CONV_SHRINK_O
#undef CONV_SETUP

__global__ void __cluster_dims__(2, 1, 1) __launch_bounds__(NTHREADS, 1)
fused_kernel(const __grid_constant__ Params p) {
  extern __shared__ uint8_t smem_raw[];
  const uint32_t sb = ((uint32_t)__cvta_generic_to_shared(smem_raw) + 1023u) & ~1023u;
  const uint32_t bars = sb + BAR_OFF;
  const uint32_t ep_slot = bars + 512;
  const int tid = threadIdx.x;
  const int cid = blockIdx.x >> 1;
  const uint32_t crank = blockIdx.x & 1;
  const int warp_id = __shfl_sync(0xffffffffu, tid >> 5, 0);

  if (tid == 256) {
    PROF(0);
    if (cid < G1_CLUSTERS) {
      prefetch_map(&p.m_x);
      prefetch_map(crank ? &p.m_wu : &p.m_wg);
      prefetch_map(&p.m_h);
    } else {
      prefetch_map(&p.m_k); prefetch_map(&p.m_v); prefetch_map(&p.m_us); prefetch_map(&p.m_u);
      prefetch_map(&p.m_h); prefetch_map(&p.m_wd); prefetch_map(&p.m_y);
    }
    for (int i = 0; i < 10; i++) {
      mbar_init(bars + (B_FULL + i) * 8, 1);
      mbar_init(bars + (B_EMPTY + i) * 8, 4);
    }
    for (int i = 0; i < 9; i++) mbar_init(bars + (B_XFULL + i) * 8, 1);
    mbar_init(bars + B_XFREE * 8, 16);
    for (int i = 0; i < 2; i++) {
      mbar_init(bars + (B_HFULL + i) * 8, 256);
      mbar_init(bars + (B_HEMPTY + i) * 8, 1);
    }
    for (int i = 0; i < 11; i++) mbar_init(bars + (B_KVFULL + i) * 8, 1);
    mbar_init(bars + B_PFREE * 8, 4);
    mbar_init(bars + B_PADONE * 8, 2);
    for (int i = 0; i < 4; i++) {
      mbar_init(bars + (B_KFULL + i) * 8, 96);
      mbar_init(bars + (B_CEMPTY + i) * 8, 128);
    }
    asm volatile("st.volatile.shared.u32 [%0], %1;" ::"r"(ep_slot), "r"(0) : "memory");
    asm volatile("fence.mbarrier_init.release.cluster;" ::: "memory");
    if (cid < G1_CLUSTERS) g1_load_x(p, sb, bars, (cid & 7) * 2 + crank);
    else if (cid < G1_CLUSTERS + G2_CLUSTERS)
      prep_load(p, sb, bars, ((cid - G1_CLUSTERS) & 7) * 2 + crank, (cid - G1_CLUSTERS) >> 3);
  }
  __syncthreads();
  cluster_arrive();

  if (cid < G1_CLUSTERS) {
    const int mblk = (cid & 7) * 2 + crank, jj = cid >> 3;
    const int nu = (jj == 4) ? 28 : 29;
    if (warp_id >= 8) {
      asm volatile("setmaxnreg.dec.sync.aligned.u32 24;");
      const int f0 = jj * G1_FSPAN;
      if (tid == 352) epoch_publish(ep_slot);
      __syncwarp();
      cluster_wait();
      if (tid == 256) {
        g1_producer(p, sb, bars, f0, nu, crank);
        g1_conv_loads(p, sb, bars, nu, (cid * 2 + crank) * NCH_G1, epoch_get(ep_slot));
      } else if (tid == 288 || tid == 320) {
        g1_store(p, sb, bars, mblk, jj, f0, nu, epoch_get(ep_slot), tid == 320);
      }
      __syncwarp();
      cluster_arrive();
      cluster_wait();
      if (tid == 352) PROF(30);
    } else {
      asm volatile("setmaxnreg.inc.sync.aligned.u32 240;");
      g1_consumer(sb, bars, mblk, jj, nu);
      g1_conv(p);
      __syncwarp();
      cluster_arrive();
      cluster_wait();
      if (tid == 0) { PROF(4); }
    }
  } else {
    const bool g2 = cid < G1_CLUSTERS + G2_CLUSTERS;
    const int idx = cid - G1_CLUSTERS;
    const int mblk = (idx & 7) * 2 + crank, ntile = idx >> 3;
    int ch0, nch;
    conv_channels_of(cid, crank, ch0, nch);
    if (tid == 352) epoch_publish(ep_slot);
    __syncwarp();
    cluster_wait();
    const uint32_t epoch = epoch_get(ep_slot);
    if (g2) prep_compute(p, sb, bars, mblk, ntile, epoch);
    if (tid == 0) PROF(13);
    if (warp_id >= 8) {
      asm volatile("setmaxnreg.dec.sync.aligned.u32 40;");
      conv_producer_side(p, sb, bars, ch0, nch, epoch, warp_id);
      if (g2 && tid == 352) wd_prefetch(p, mblk, ntile);
      if (g2 && warp_id <= 9) g2_producer_a(p, sb, bars, mblk, epoch, warp_id - 8);
      if (g2 && tid == 320) g2_producer_b(p, sb, bars, mblk, ntile, crank, epoch);
      __syncwarp();
      cluster_arrive();
      cluster_wait();
      if (tid == 352) PROF(30);
    } else {
      asm volatile("setmaxnreg.inc.sync.aligned.u32 232;");
      conv_consumer_side(p, sb, bars, ch0, nch, epoch);
      if (g2) g2_consumer(p, sb, bars, mblk, ntile);
      __syncwarp();
      cluster_arrive();
      cluster_wait();
      if (tid == 0) { PROF(4); }
    }
  }
}

typedef CUresult (*EncodeFn)(CUtensorMap*, CUtensorMapDataType, cuuint32_t, void*, const cuuint64_t*, const cuuint64_t*,
                             const cuuint32_t*, const cuuint32_t*, CUtensorMapInterleave, CUtensorMapSwizzle,
                             CUtensorMapL2promotion, CUtensorMapFloatOOBfill);

static void encode(EncodeFn fn, CUtensorMap* m, const void* ptr, int rank, const cuuint64_t* dims, const cuuint64_t* strides,
                   const cuuint32_t* box, CUtensorMapSwizzle swz, CUtensorMapL2promotion promo) {
  cuuint32_t es[5] = {1, 1, 1, 1, 1};
  fn(m, CU_TENSOR_MAP_DATA_TYPE_BFLOAT16, rank, const_cast<void*>(ptr), dims, strides, box, es,
     CU_TENSOR_MAP_INTERLEAVE_NONE, swz, promo, CU_TENSOR_MAP_FLOAT_OOB_FILL_NONE);
}

}

extern "C" void kernel_launch(void* const* d_in, const int* in_sizes, int n_in, void* d_out, int out_size) {
  using namespace ffn;
  (void)in_sizes; (void)n_in; (void)out_size;
  static EncodeFn enc = nullptr;
  if (!enc) {
    void* fn = nullptr;
    cudaDriverEntryPointQueryResult qr;
    cudaGetDriverEntryPoint("cuTensorMapEncodeTiled", &fn, cudaEnableDefault, &qr);
    enc = (EncodeFn)fn;
    cudaFuncSetAttribute(fused_kernel, cudaFuncAttributeMaxDynamicSharedMemorySize, SMEM_BYTES);
  }
  const void* q = d_in[0];
  const void* k = d_in[1];
  const void* v = d_in[2];
  const void* wg = d_in[7];
  const void* wu = d_in[8];
  const void* wd = d_in[9];
  void *h, *uT, *yT;
  cudaGetSymbolAddress(&h, g_h);
  cudaGetSymbolAddress(&uT, g_uT);
  cudaGetSymbolAddress(&yT, g_yT);

  Params p;
  const CUtensorMapL2promotion P128 = CU_TENSOR_MAP_L2_PROMOTION_L2_128B, P256 = CU_TENSOR_MAP_L2_PROMOTION_L2_256B;
  {
    cuuint64_t dims[2] = {D_, S_}, str[1] = {D_ * 2};
    cuuint32_t box[2] = {64, 128};
    encode(enc, &p.m_x, q, 2, dims, str, box, CU_TENSOR_MAP_SWIZZLE_128B, P128);
    cuuint32_t boxk[2] = {64, 132};
    encode(enc, &p.m_k, k, 2, dims, str, boxk, CU_TENSOR_MAP_SWIZZLE_NONE, P128);
    encode(enc, &p.m_v, v, 2, dims, str, box, CU_TENSOR_MAP_SWIZZLE_NONE, P128);
  }
  {
    cuuint64_t dims[2] = {F_, D_}, str[1] = {F_ * 2};
    cuuint32_t box[2] = {32, 192};
    encode(enc, &p.m_wg, wg, 2, dims, str, box, CU_TENSOR_MAP_SWIZZLE_64B, P256);
    encode(enc, &p.m_wu, wu, 2, dims, str, box, CU_TENSOR_MAP_SWIZZLE_64B, P256);
  }
  {
    cuuint64_t dims[3] = {64, F_, 9}, str[2] = {D_ * 2, 128};
    cuuint32_t box[3] = {64, 32, 3};
    encode(enc, &p.m_wd, wd, 3, dims, str, box, CU_TENSOR_MAP_SWIZZLE_128B, P128);
  }
  {
    cuuint64_t dims[2] = {F_, S_}, str[1] = {F_ * 2};
    cuuint32_t box[2] = {32, 128};
    encode(enc, &p.m_h, h, 2, dims, str, box, CU_TENSOR_MAP_SWIZZLE_64B, CU_TENSOR_MAP_L2_PROMOTION_NONE);
  }
  {
    cuuint64_t dims[4] = {8, 128, 2, D_}, str[3] = {32, 16, S_ * 2};
    cuuint32_t box[4] = {8, 128, 1, 1};
    encode(enc, &p.m_u, uT, 4, dims, str, box, CU_TENSOR_MAP_SWIZZLE_NONE, CU_TENSOR_MAP_L2_PROMOTION_NONE);
  }
  {
    cuuint64_t dims[2] = {S_, D_}, str[1] = {S_ * 2};
    cuuint32_t box[2] = {64, 192};
    encode(enc, &p.m_y, yT, 2, dims, str, box, CU_TENSOR_MAP_SWIZZLE_128B, CU_TENSOR_MAP_L2_PROMOTION_NONE);
    encode(enc, &p.m_us, uT, 2, dims, str, box, CU_TENSOR_MAP_SWIZZLE_128B, CU_TENSOR_MAP_L2_PROMOTION_NONE);
  }
  p.x = (const __nv_bfloat16*)q;
  p.out = (__nv_bfloat16*)d_out;
  p.shift_k = (const __nv_bfloat16*)d_in[3];
  p.ssm_k = (const __nv_bfloat16*)d_in[4];
  p.ssm_D = (const __nv_bfloat16*)d_in[5];
  p.zero = 0;

  fused_kernel<<<NCTA, NTHREADS, SMEM_BYTES, cudaStreamPerThread>>>(p);
}
```
